```python
import torch

def _softmax(x, axis=-1):
    return torch.softmax(x, dim=axis)

def _gelu(x):
    return torch.nn.functional.gelu(x, approximate='tanh')

def _silu(x):
    return torch.nn.functional.silu(x)

def _sigmoid(x):
    return torch.sigmoid(x)

def _layernorm(x, axis=-1, eps=1e-05):
    m = x.mean(dim=axis, keepdim=True)
    v = x.var(dim=axis, keepdim=True, unbiased=False)
    return (x - m) / torch.sqrt(v + eps)

def _scatter_add(tgt, idx, src, axis=0):
    return tgt.clone().index_add_(axis, idx, src)

def _segment_sum(src, seg, n):
    out = torch.zeros((n,) + src.shape[1:], dtype=src.dtype)
    return out.index_add_(0, seg, src)

def _pad(x, pw):
    flat = tuple((v for pair in reversed(pw) for v in pair))
    return torch.nn.functional.pad(x, flat)
kernel_name = 'recurrent_scan__softmax_full_mha__mixer_gmlp__prompt'

def setup_inputs():

    _w = lambda a: (lambda t: t.to(torch.bfloat16) if t.is_floating_point() else t)(torch.as_tensor(a))

    def _A_setup():
        B, S, D = (1, 2048, 512)
        return {'x': _w((lambda *s: torch.randn(*s, dtype=torch.bfloat16) * 0.05)(B, S, D)), 'wqkv': _w((lambda *s: torch.randn(*s, dtype=torch.bfloat16) * 0.05)(D, 3 * D)), 'wo': _w((lambda *s: torch.randn(*s, dtype=torch.bfloat16) * 0.05)(D, D))}
    _A_in = _A_setup()

    def _B_setup():
        B, S, D, F = (1, 2048, 512, 1792)
        Fh = F // 2
        return {'x': _w((lambda *s: torch.randn(*s, dtype=torch.bfloat16) * 0.05)(B, S, D)), 'w_in': _w((lambda *s: torch.randn(*s, dtype=torch.bfloat16) * 0.8)(D, 2 * Fh)), 'w_sp': _w(0.01 * (lambda *s: torch.randn(*s, dtype=torch.bfloat16) * 0.8)(S, S)), 'b_sp': _w(1.0 + 0.01 * (lambda *s: torch.randn(*s, dtype=torch.bfloat16) * 0.05)(S)), 'w_out': _w((lambda *s: torch.randn(*s, dtype=torch.bfloat16) * 0.05)(Fh, D))}
    _B_in = _B_setup()
    return {'A_x': _A_in['x'], 'A_wqkv': _A_in['wqkv'], 'A_wo': _A_in['wo'], 'B_x': _B_in['x'], 'B_w_in': _B_in['w_in'], 'B_w_sp': _B_in['w_sp'], 'B_b_sp': _B_in['b_sp'], 'B_w_out': _B_in['w_out']}

def reference(A_x, A_wqkv, A_wo, B_x, B_w_in, B_w_sp, B_b_sp, B_w_out):

    def _A_ref(x, wqkv, wo):
        B, S, D = x.shape
        H = 32
        Dh = D // H
        qkv = (lambda x, *d: x.permute(*d))((x @ wqkv).reshape(B, S, 3, H, Dh), 2, 0, 3, 1, 4)
        q, k, v = (qkv[0], qkv[1], qkv[2])
        scale = Dh ** (-0.5)
        scores = torch.einsum('bhqd,bhkd->bhqk', q, k) * scale
        p = _softmax(scores, axis=-1)
        o = torch.einsum('bhqk,bhkd->bhqd', p, v)
        return (lambda x, *d: x.permute(*d))(o, 0, 2, 1, 3).reshape(B, S, D) @ wo

    def _B_ref(x, w_in, w_sp, b_sp, w_out):
        B, S, D = x.shape
        F = w_in.shape[-1]
        Fh = F // 2
        z = _gelu(torch.einsum('bsd,df->bsf', x, w_in))
        z1 = z[..., :Fh].clone()
        z2 = _layernorm(z[..., Fh:], axis=-1)
        g = torch.einsum('ts,bsf->btf', w_sp, z2) + b_sp[None, :, None]
        return torch.einsum('bsf,fd->bsd', z1 * g, w_out)
    x = A_x
    xn = _layernorm(x, axis=-1)
    s = _A_ref(xn, A_wqkv, A_wo)
    g = _silu(_B_ref(xn, B_w_in, B_w_sp, B_b_sp, B_w_out))
    return x + s * g
```

```cpp
#include <cuda_runtime.h>
#include <cuda_bf16.h>
#include <cuda_fp16.h>
#include <cuda.h>
#include <stdint.h>

typedef __nv_bfloat16 bf16;
constexpr int S_ = 2048, D_ = 512, H_ = 32, FH_ = 896;

__device__ __align__(1024) uint4 g_qkv[3 * H_ * S_ * 2];
__device__ __align__(1024) uint4 g_qkb[2 * H_ * 128 * 32];
__device__ __align__(64) uint2 g_nrm[8 * 128 * 8];
__device__ __align__(64) uint4 g_rs[S_];
__device__ __align__(64) uint4 g_cs[3328 / 2];
__device__ __align__(64) uint4 g_stat[8 * S_];
__device__ __align__(1024) uint4 g_z1[128 * 56 * 32];
__device__ __align__(1024) uint4 g_z2t[32 * FH_ * 8];
__device__ float4 g_part[128 * 2 * 3 * 128];
__device__ __align__(64) uint4 g_hp[128 * 5 * 128];
__device__ __align__(1024) bf16 g_u[S_ * FH_];
__device__ __align__(1024) bf16 g_o[S_ * D_];
constexpr int C_QKV = 0, C_Z2 = 32, C_U = 40, C_O = 56, C_OL = 60, C_TICKET = 92, C_NUM = 93;
__device__ unsigned g_cnt[C_NUM * 8];

__device__ __forceinline__ uint32_t s2u(const void* p) { return (uint32_t)__cvta_generic_to_shared(p); }
__device__ __forceinline__ void wfence() { asm volatile("wgmma.fence.sync.aligned;" ::: "memory"); }
__device__ __forceinline__ void wcommit() { asm volatile("wgmma.commit_group.sync.aligned;" ::: "memory"); }
template <int N> __device__ __forceinline__ void wwait() { asm volatile("wgmma.wait_group.sync.aligned %0;" ::"n"(N) : "memory"); }
__device__ __forceinline__ uint64_t mkdesc(uint32_t addr, uint32_t lbo, uint32_t sbo, uint32_t sw) {
  return (uint64_t)((addr & 0x3FFFF) >> 4) | ((uint64_t)(lbo >> 4) << 16) | ((uint64_t)(sbo >> 4) << 32) | ((uint64_t)sw << 62);
}
__device__ __forceinline__ void mbar_init(uint32_t b, int c) { asm volatile("mbarrier.init.shared.b64 [%0], %1;" ::"r"(b), "r"(c)); }
__device__ __forceinline__ void mbar_expect(uint32_t b, uint32_t tx) { asm volatile("mbarrier.arrive.expect_tx.shared.b64 _, [%0], %1;" ::"r"(b), "r"(tx) : "memory"); }
__device__ __forceinline__ void mbar_arrive(uint32_t b) { asm volatile("mbarrier.arrive.shared.b64 _, [%0];" ::"r"(b) : "memory"); }
__device__ __forceinline__ void mbar_wait(uint32_t b, uint32_t ph) {
  asm volatile("{.reg .pred p; .reg .u32 c0, c1;\n"
               "mbarrier.try_wait.parity.shared.b64 p, [%0], %1;\n @p bra WAITD;\n mov.u32 c0, %%clock;\n"
               "WAITL: mbarrier.try_wait.parity.shared.b64 p, [%0], %1;\n"
               "@p bra WAITD;\n mov.u32 c1, %%clock;\n sub.u32 c1, c1, c0;\n setp.lt.u32 p, c1, 67108864;\n @p bra WAITL;\n"
               "WAITD: }" ::"r"(b), "r"(ph) : "memory");
}
__device__ __forceinline__ uint64_t opaque(uint64_t v) { asm volatile("" : "+l"(v)); return v; }
__device__ __forceinline__ void tma2d(uint32_t dst, const CUtensorMap* m, int c0, int c1, uint32_t bar) {
  asm volatile("cp.async.bulk.tensor.2d.shared::cluster.global.mbarrier::complete_tx::bytes [%0], [%1, {%3, %4}], [%2];"
               ::"r"(dst), "l"(m), "r"(bar), "r"(c0), "r"(c1) : "memory");
}
__device__ __forceinline__ void bulk_ld(uint32_t dst, const void* src, uint32_t bytes, uint32_t bar) {
  asm volatile("cp.async.bulk.shared::cluster.global.mbarrier::complete_tx::bytes [%0], [%1], %2, [%3];"
               ::"r"(dst), "l"(src), "r"(bytes), "r"(bar) : "memory");
}
__device__ __forceinline__ void bulk_st(void* dst, uint32_t src, uint32_t bytes) {
  asm volatile("cp.async.bulk.global.shared::cta.bulk_group [%0], [%1], %2;" ::"l"(dst), "r"(src), "r"(bytes) : "memory");
}
__device__ __forceinline__ void tma2d_st(const CUtensorMap* m, uint32_t src, int c0, int c1) {
  asm volatile("cp.async.bulk.tensor.2d.global.shared::cta.bulk_group [%0, {%2, %3}], [%1];" ::"l"(m), "r"(src), "r"(c0), "r"(c1) : "memory");
}
__device__ __forceinline__ void bulk_commit() { asm volatile("cp.async.bulk.commit_group;" ::: "memory"); }
__device__ __forceinline__ void bulk_wait0() { asm volatile("cp.async.bulk.wait_group 0;" ::: "memory"); }
__device__ __forceinline__ void fence_async_smem() { asm volatile("fence.proxy.async.shared::cta;" ::: "memory"); }
__device__ __forceinline__ void nbar(int id, int n) { asm volatile("bar.sync %0, %1;" ::"r"(id), "r"(n) : "memory"); }
__device__ __forceinline__ void stsm4(uint32_t a, uint32_t r0, uint32_t r1, uint32_t r2, uint32_t r3) {
  asm volatile("stmatrix.sync.aligned.m8n8.x4.shared.b16 [%0], {%1,%2,%3,%4};" ::"r"(a), "r"(r0), "r"(r1), "r"(r2), "r"(r3) : "memory");
}
__device__ __forceinline__ void stsm4t(uint32_t a, uint32_t r0, uint32_t r1, uint32_t r2, uint32_t r3) {
  asm volatile("stmatrix.sync.aligned.m8n8.x4.trans.shared.b16 [%0], {%1,%2,%3,%4};" ::"r"(a), "r"(r0), "r"(r1), "r"(r2), "r"(r3) : "memory");
}
__device__ __forceinline__ float ex2(float x) { float y; asm("ex2.approx.ftz.f32 %0,%1;" : "=f"(y) : "f"(x)); return y; }
__device__ __forceinline__ float tanh_fast(float x) { float y; asm("tanh.approx.f32 %0,%1;" : "=f"(y) : "f"(x)); return y; }
__device__ __forceinline__ uint32_t packbf(float lo, float hi) { uint32_t y; asm("cvt.rn.bf16x2.f32 %0,%1,%2;" : "=r"(y) : "f"(hi), "f"(lo)); return y; }
__device__ __forceinline__ uint32_t packh(float lo, float hi) { uint32_t y; asm("cvt.rn.f16x2.f32 %0,%1,%2;" : "=r"(y) : "f"(hi), "f"(lo)); return y; }
__device__ __forceinline__ float bflo(uint32_t u) { return __uint_as_float(u << 16); }
__device__ __forceinline__ float bfhi(uint32_t u) { return __uint_as_float(u & 0xffff0000u); }
template <int N> __device__ __forceinline__ void fence_regs(float* d) {
#pragma unroll
  for (int i = 0; i < N; i++) asm volatile("" : "+f"(d[i])::"memory");
}
template <int N> __device__ __forceinline__ void fence_regs(uint32_t* d) {
#pragma unroll
  for (int i = 0; i < N; i++) asm volatile("" : "+r"(d[i])::"memory");
}
__device__ __forceinline__ float rbf(float x) { return __bfloat162float(__float2bfloat16(x)); }
__device__ __forceinline__ float2 ln_coef(float mean, float var) {
  const float r = 1.f / rbf(sqrtf(rbf(rbf(var) + 1e-5f)));
  return make_float2(r, -rbf(mean) * r);
}
__device__ __forceinline__ float gelu_half(float hx) {
  const float w = fmaf(hx * hx, 8.f * 0.044715f * 0.7978845608028654f, 2.f * 0.7978845608028654f);
  return fmaf(hx, tanh_fast(hx * w), hx);
}

__device__ __forceinline__ void mm192t(float* d, uint64_t da, uint64_t db, int sd){
  asm volatile("{.reg .pred p; setp.ne.b32 p, %98, 0;\n wgmma.mma_async.sync.aligned.m64n192k16.f32.bf16.bf16 {%0,%1,%2,%3,%4,%5,%6,%7,%8,%9,%10,%11,%12,%13,%14,%15,%16,%17,%18,%19,%20,%21,%22,%23,%24,%25,%26,%27,%28,%29,%30,%31,%32,%33,%34,%35,%36,%37,%38,%39,%40,%41,%42,%43,%44,%45,%46,%47,%48,%49,%50,%51,%52,%53,%54,%55,%56,%57,%58,%59,%60,%61,%62,%63,%64,%65,%66,%67,%68,%69,%70,%71,%72,%73,%74,%75,%76,%77,%78,%79,%80,%81,%82,%83,%84,%85,%86,%87,%88,%89,%90,%91,%92,%93,%94,%95}, %96, %97, p, 1, 1, 0, 1;}"
  : "+f"(d[0]),"+f"(d[1]),"+f"(d[2]),"+f"(d[3]),"+f"(d[4]),"+f"(d[5]),"+f"(d[6]),"+f"(d[7]),"+f"(d[8]),"+f"(d[9]),"+f"(d[10]),"+f"(d[11]),"+f"(d[12]),"+f"(d[13]),"+f"(d[14]),"+f"(d[15]),"+f"(d[16]),"+f"(d[17]),"+f"(d[18]),"+f"(d[19]),"+f"(d[20]),"+f"(d[21]),"+f"(d[22]),"+f"(d[23]),"+f"(d[24]),"+f"(d[25]),"+f"(d[26]),"+f"(d[27]),"+f"(d[28]),"+f"(d[29]),"+f"(d[30]),"+f"(d[31]),"+f"(d[32]),"+f"(d[33]),"+f"(d[34]),"+f"(d[35]),"+f"(d[36]),"+f"(d[37]),"+f"(d[38]),"+f"(d[39]),"+f"(d[40]),"+f"(d[41]),"+f"(d[42]),"+f"(d[43]),"+f"(d[44]),"+f"(d[45]),"+f"(d[46]),"+f"(d[47]),"+f"(d[48]),"+f"(d[49]),"+f"(d[50]),"+f"(d[51]),"+f"(d[52]),"+f"(d[53]),"+f"(d[54]),"+f"(d[55]),"+f"(d[56]),"+f"(d[57]),"+f"(d[58]),"+f"(d[59]),"+f"(d[60]),"+f"(d[61]),"+f"(d[62]),"+f"(d[63]),"+f"(d[64]),"+f"(d[65]),"+f"(d[66]),"+f"(d[67]),"+f"(d[68]),"+f"(d[69]),"+f"(d[70]),"+f"(d[71]),"+f"(d[72]),"+f"(d[73]),"+f"(d[74]),"+f"(d[75]),"+f"(d[76]),"+f"(d[77]),"+f"(d[78]),"+f"(d[79]),"+f"(d[80]),"+f"(d[81]),"+f"(d[82]),"+f"(d[83]),"+f"(d[84]),"+f"(d[85]),"+f"(d[86]),"+f"(d[87]),"+f"(d[88]),"+f"(d[89]),"+f"(d[90]),"+f"(d[91]),"+f"(d[92]),"+f"(d[93]),"+f"(d[94]),"+f"(d[95])
  : "l"(da),"l"(db),"r"(sd));
}
__device__ __forceinline__ void mm112t(float* d, uint64_t da, uint64_t db, int sd){
  asm volatile("{.reg .pred p; setp.ne.b32 p, %58, 0;\n wgmma.mma_async.sync.aligned.m64n112k16.f32.bf16.bf16 {%0,%1,%2,%3,%4,%5,%6,%7,%8,%9,%10,%11,%12,%13,%14,%15,%16,%17,%18,%19,%20,%21,%22,%23,%24,%25,%26,%27,%28,%29,%30,%31,%32,%33,%34,%35,%36,%37,%38,%39,%40,%41,%42,%43,%44,%45,%46,%47,%48,%49,%50,%51,%52,%53,%54,%55}, %56, %57, p, 1, 1, 0, 1;}"
  : "+f"(d[0]),"+f"(d[1]),"+f"(d[2]),"+f"(d[3]),"+f"(d[4]),"+f"(d[5]),"+f"(d[6]),"+f"(d[7]),"+f"(d[8]),"+f"(d[9]),"+f"(d[10]),"+f"(d[11]),"+f"(d[12]),"+f"(d[13]),"+f"(d[14]),"+f"(d[15]),"+f"(d[16]),"+f"(d[17]),"+f"(d[18]),"+f"(d[19]),"+f"(d[20]),"+f"(d[21]),"+f"(d[22]),"+f"(d[23]),"+f"(d[24]),"+f"(d[25]),"+f"(d[26]),"+f"(d[27]),"+f"(d[28]),"+f"(d[29]),"+f"(d[30]),"+f"(d[31]),"+f"(d[32]),"+f"(d[33]),"+f"(d[34]),"+f"(d[35]),"+f"(d[36]),"+f"(d[37]),"+f"(d[38]),"+f"(d[39]),"+f"(d[40]),"+f"(d[41]),"+f"(d[42]),"+f"(d[43]),"+f"(d[44]),"+f"(d[45]),"+f"(d[46]),"+f"(d[47]),"+f"(d[48]),"+f"(d[49]),"+f"(d[50]),"+f"(d[51]),"+f"(d[52]),"+f"(d[53]),"+f"(d[54]),"+f"(d[55])
  : "l"(da),"l"(db),"r"(sd));
}
__device__ __forceinline__ void mm112(float* d, uint64_t da, uint64_t db, int sd){
  asm volatile("{.reg .pred p; setp.ne.b32 p, %58, 0;\n wgmma.mma_async.sync.aligned.m64n112k16.f32.bf16.bf16 {%0,%1,%2,%3,%4,%5,%6,%7,%8,%9,%10,%11,%12,%13,%14,%15,%16,%17,%18,%19,%20,%21,%22,%23,%24,%25,%26,%27,%28,%29,%30,%31,%32,%33,%34,%35,%36,%37,%38,%39,%40,%41,%42,%43,%44,%45,%46,%47,%48,%49,%50,%51,%52,%53,%54,%55}, %56, %57, p, 1, 1, 0, 0;}"
  : "+f"(d[0]),"+f"(d[1]),"+f"(d[2]),"+f"(d[3]),"+f"(d[4]),"+f"(d[5]),"+f"(d[6]),"+f"(d[7]),"+f"(d[8]),"+f"(d[9]),"+f"(d[10]),"+f"(d[11]),"+f"(d[12]),"+f"(d[13]),"+f"(d[14]),"+f"(d[15]),"+f"(d[16]),"+f"(d[17]),"+f"(d[18]),"+f"(d[19]),"+f"(d[20]),"+f"(d[21]),"+f"(d[22]),"+f"(d[23]),"+f"(d[24]),"+f"(d[25]),"+f"(d[26]),"+f"(d[27]),"+f"(d[28]),"+f"(d[29]),"+f"(d[30]),"+f"(d[31]),"+f"(d[32]),"+f"(d[33]),"+f"(d[34]),"+f"(d[35]),"+f"(d[36]),"+f"(d[37]),"+f"(d[38]),"+f"(d[39]),"+f"(d[40]),"+f"(d[41]),"+f"(d[42]),"+f"(d[43]),"+f"(d[44]),"+f"(d[45]),"+f"(d[46]),"+f"(d[47]),"+f"(d[48]),"+f"(d[49]),"+f"(d[50]),"+f"(d[51]),"+f"(d[52]),"+f"(d[53]),"+f"(d[54]),"+f"(d[55])
  : "l"(da),"l"(db),"r"(sd));
}
__device__ __forceinline__ void mm128t(float* d, uint64_t da, uint64_t db, int sd){
  asm volatile("{.reg .pred p; setp.ne.b32 p, %66, 0;\n wgmma.mma_async.sync.aligned.m64n128k16.f32.bf16.bf16 {%0,%1,%2,%3,%4,%5,%6,%7,%8,%9,%10,%11,%12,%13,%14,%15,%16,%17,%18,%19,%20,%21,%22,%23,%24,%25,%26,%27,%28,%29,%30,%31,%32,%33,%34,%35,%36,%37,%38,%39,%40,%41,%42,%43,%44,%45,%46,%47,%48,%49,%50,%51,%52,%53,%54,%55,%56,%57,%58,%59,%60,%61,%62,%63}, %64, %65, p, 1, 1, 0, 1;}"
  : "+f"(d[0]),"+f"(d[1]),"+f"(d[2]),"+f"(d[3]),"+f"(d[4]),"+f"(d[5]),"+f"(d[6]),"+f"(d[7]),"+f"(d[8]),"+f"(d[9]),"+f"(d[10]),"+f"(d[11]),"+f"(d[12]),"+f"(d[13]),"+f"(d[14]),"+f"(d[15]),"+f"(d[16]),"+f"(d[17]),"+f"(d[18]),"+f"(d[19]),"+f"(d[20]),"+f"(d[21]),"+f"(d[22]),"+f"(d[23]),"+f"(d[24]),"+f"(d[25]),"+f"(d[26]),"+f"(d[27]),"+f"(d[28]),"+f"(d[29]),"+f"(d[30]),"+f"(d[31]),"+f"(d[32]),"+f"(d[33]),"+f"(d[34]),"+f"(d[35]),"+f"(d[36]),"+f"(d[37]),"+f"(d[38]),"+f"(d[39]),"+f"(d[40]),"+f"(d[41]),"+f"(d[42]),"+f"(d[43]),"+f"(d[44]),"+f"(d[45]),"+f"(d[46]),"+f"(d[47]),"+f"(d[48]),"+f"(d[49]),"+f"(d[50]),"+f"(d[51]),"+f"(d[52]),"+f"(d[53]),"+f"(d[54]),"+f"(d[55]),"+f"(d[56]),"+f"(d[57]),"+f"(d[58]),"+f"(d[59]),"+f"(d[60]),"+f"(d[61]),"+f"(d[62]),"+f"(d[63])
  : "l"(da),"l"(db),"r"(sd));
}
__device__ __forceinline__ void qk_f32(float* d, const uint32_t* a, uint64_t db){
  asm volatile("wgmma.mma_async.sync.aligned.m64n24k16.f32.f16.f16 {%0,%1,%2,%3,%4,%5,%6,%7,%8,%9,%10,%11}, {%12,%13,%14,%15}, %16, 0, 1, 1, 0;"
  : "+f"(d[0]),"+f"(d[1]),"+f"(d[2]),"+f"(d[3]),"+f"(d[4]),"+f"(d[5]),"+f"(d[6]),"+f"(d[7]),"+f"(d[8]),"+f"(d[9]),"+f"(d[10]),"+f"(d[11])
  : "r"(a[0]),"r"(a[1]),"r"(a[2]),"r"(a[3]),"l"(db));
}
__device__ __forceinline__ void qk_f16(uint32_t* d, const uint32_t* a, uint64_t db){
  asm volatile("wgmma.mma_async.sync.aligned.m64n40k16.f16.f16.f16 {%0,%1,%2,%3,%4,%5,%6,%7,%8,%9}, {%10,%11,%12,%13}, %14, 0, 1, 1, 0;"
  : "+r"(d[0]),"+r"(d[1]),"+r"(d[2]),"+r"(d[3]),"+r"(d[4]),"+r"(d[5]),"+r"(d[6]),"+r"(d[7]),"+r"(d[8]),"+r"(d[9])
  : "r"(a[0]),"r"(a[1]),"r"(a[2]),"r"(a[3]),"l"(db));
}
__device__ __forceinline__ void pv24(float* d, const uint32_t* a, uint64_t db){
  asm volatile("wgmma.mma_async.sync.aligned.m64n24k16.f32.bf16.bf16 {%0,%1,%2,%3,%4,%5,%6,%7,%8,%9,%10,%11}, {%12,%13,%14,%15}, %16, 1, 1, 1, 1;"
  : "+f"(d[0]),"+f"(d[1]),"+f"(d[2]),"+f"(d[3]),"+f"(d[4]),"+f"(d[5]),"+f"(d[6]),"+f"(d[7]),"+f"(d[8]),"+f"(d[9]),"+f"(d[10]),"+f"(d[11])
  : "r"(a[0]),"r"(a[1]),"r"(a[2]),"r"(a[3]),"l"(db));
}
__device__ __forceinline__ void qk64(float* d, const uint32_t* a, uint64_t db){
  asm volatile("wgmma.mma_async.sync.aligned.m64n64k16.f32.f16.f16 {%0,%1,%2,%3,%4,%5,%6,%7,%8,%9,%10,%11,%12,%13,%14,%15,%16,%17,%18,%19,%20,%21,%22,%23,%24,%25,%26,%27,%28,%29,%30,%31}, {%32,%33,%34,%35}, %36, 0, 1, 1, 0;"
  : "+f"(d[0]),"+f"(d[1]),"+f"(d[2]),"+f"(d[3]),"+f"(d[4]),"+f"(d[5]),"+f"(d[6]),"+f"(d[7]),"+f"(d[8]),"+f"(d[9]),"+f"(d[10]),"+f"(d[11]),"+f"(d[12]),"+f"(d[13]),"+f"(d[14]),"+f"(d[15]),"+f"(d[16]),"+f"(d[17]),"+f"(d[18]),"+f"(d[19]),"+f"(d[20]),"+f"(d[21]),"+f"(d[22]),"+f"(d[23]),"+f"(d[24]),"+f"(d[25]),"+f"(d[26]),"+f"(d[27]),"+f"(d[28]),"+f"(d[29]),"+f"(d[30]),"+f"(d[31])
  : "r"(a[0]),"r"(a[1]),"r"(a[2]),"r"(a[3]),"l"(db));
}

constexpr int STRIPAT = 2, SPLA = 5, SPLB = 2;
constexpr float QSCALE = 0.25f * 1.4426950408889634f;
constexpr float VSC = 1.4140625f, VSP = 2.98023223876953125e-08f;
constexpr int NMU = 24;
constexpr float NRM_HI = 1048576.f, NRM_LO = 9.5367431640625e-07f;

__device__ __forceinline__ float2 lds2(uint32_t a) {
  float2 v; asm volatile("ld.shared.v2.f32 {%0,%1}, [%2];" : "=f"(v.x), "=f"(v.y) : "r"(a) : "memory"); return v;
}
__device__ __forceinline__ bool elect1() {
  uint32_t p;
  asm volatile("{.reg .pred P; elect.sync _|P, 0xffffffff; selp.u32 %0, 1, 0, P;}" : "=r"(p));
  return p != 0;
}
__device__ __forceinline__ void nbar_arrive(int id, int n) { asm volatile("bar.arrive %0, %1;" ::"r"(id), "r"(n) : "memory"); }
__device__ __forceinline__ void fence_async_glb() { asm volatile("fence.proxy.async.global;" ::: "memory"); }
__device__ __forceinline__ void cnt_add_rel(int c) { asm volatile("red.release.gpu.global.add.u32 [%0], 1;" ::"l"(&g_cnt[c * 8]) : "memory"); }
__device__ __forceinline__ void cnt_add_rlx(int c) { asm volatile("red.relaxed.gpu.global.add.u32 [%0], 1;" ::"l"(&g_cnt[c * 8]) : "memory"); }
__device__ __forceinline__ void cnt_wait(int c, unsigned target) {
  unsigned v; int it = 0;
  do { asm volatile("ld.acquire.gpu.global.u32 %0, [%1];" : "=r"(v) : "l"(&g_cnt[c * 8]) : "memory"); } while ((int)(v - target) < 0 && ++it < (1 << 17));
  fence_async_glb();
}
__device__ __forceinline__ void put2(uint4* p, float a, float b, uint32_t tag) {
  asm volatile("st.relaxed.gpu.global.v4.u32 [%0], {%1,%2,%3,%2};" ::"l"(p), "r"(__float_as_uint(a)), "r"(tag), "r"(__float_as_uint(b)) : "memory");
}
__device__ __forceinline__ uint4 ldv4(const uint4* p) {
  uint4 v; asm volatile("ld.relaxed.gpu.global.v4.u32 {%0,%1,%2,%3}, [%4];" : "=r"(v.x), "=r"(v.y), "=r"(v.z), "=r"(v.w) : "l"(p) : "memory"); return v;
}
__device__ __forceinline__ int nrm_idx(int ty, int head, int rg) { return ((head >> 2) * 128 + rg) * 8 + ty * 4 + (head & 3); }
__device__ __forceinline__ void mbar_arrive_peer(uint32_t b, int rank) {
  uint32_t r;
  asm volatile("mapa.shared::cluster.u32 %0, %1, %2;" : "=r"(r) : "r"(b), "r"(rank ^ 1));
  asm volatile("mbarrier.arrive.shared::cluster.b64 _, [%0];" ::"r"(r) : "memory");
}
__device__ __forceinline__ void tma2d_mc(uint32_t dst, const CUtensorMap* m, int c0, int c1, uint32_t bar) {
  asm volatile("cp.async.bulk.tensor.2d.shared::cluster.global.mbarrier::complete_tx::bytes.multicast::cluster [%0], [%1, {%3, %4}], [%2], %5;"
               ::"r"(dst), "l"(m), "r"(bar), "r"(c0), "r"(c1), "h"((uint16_t)3) : "memory");
}
__device__ __forceinline__ void bulk_ld_mc(uint32_t dst, const void* src, uint32_t bytes, uint32_t bar) {
  asm volatile("cp.async.bulk.shared::cluster.global.mbarrier::complete_tx::bytes.multicast::cluster [%0], [%1], %2, [%3], %4;"
               ::"r"(dst), "l"(src), "r"(bytes), "r"(bar), "h"((uint16_t)3) : "memory");
}
__device__ __forceinline__ void l2_prefetch(const void* p, uint32_t bytes) {
  asm volatile("cp.async.bulk.prefetch.L2.global [%0], %1;" ::"l"(p), "r"(bytes) : "memory");
}

__device__ __forceinline__ uint32_t hadd2(uint32_t a, uint32_t b) { uint32_t y; asm("add.rn.f16x2 %0,%1,%2;" : "=r"(y) : "r"(a), "r"(b)); return y; }
__device__ __forceinline__ uint32_t hfma2(uint32_t a, uint32_t b, uint32_t c) { uint32_t y; asm("fma.rn.f16x2 %0,%1,%2,%3;" : "=r"(y) : "r"(a), "r"(b), "r"(c)); return y; }
__device__ __forceinline__ uint32_t hfma2n(uint32_t a, uint32_t b, uint32_t c) {
  uint32_t y; asm("{.reg .b32 n; neg.f16x2 n, %3; fma.rn.f16x2 %0,%1,%2,n;}" : "=r"(y) : "r"(a), "r"(b), "r"(c)); return y;
}
__device__ __forceinline__ uint32_t ex2h2(uint32_t h) {
  const uint32_t t = hadd2(h, 0x65D765D7u);
  const uint32_t w = hfma2(t, 0x3EE03EE0u, 0xE906E906u);
  const uint32_t u = hfma2n(h, 0x3EE03EE0u, w);
  const uint32_t v = hfma2(u, u, 0x4C8D4C8Du);
  const uint32_t y = hfma2(v, u, 0x600A603Du);
  return t * 128u + y;
}
constexpr uint64_t INCV = (uint64_t)32 - ((uint64_t)32 << 16);
__device__ __forceinline__ void att_qk(float* sf, uint32_t* sh, const uint32_t* q, uint64_t dk) {
  qk_f32(sf, q, dk);
  qk_f16(sh, q, dk + NMU * 2);
}
__device__ __forceinline__ void att_step(float* sf, uint32_t* sh, uint32_t* p, float* o, const uint32_t* q, uint64_t dv, uint64_t dk, bool doqk) {
#pragma unroll
  for (int i = 0; i < 10; i++) {
    if (i < 6) p[i] = packbf(ex2(sf[2 * i]), ex2(sf[2 * i + 1]));
    p[6 + i] = ex2h2(sh[i]);
  }
  wfence();
#pragma unroll
  for (int j = 0; j < 4; j++) {
    pv24(o, p + 4 * j, dv + j * INCV + ((uint64_t)(j >= 2 ? 32 : j * 16) << 16));
    if (j == 1) wcommit();
  }
  if (doqk) att_qk(sf, sh, q, dk);
  wcommit();
}
__device__ __noinline__ void att_fallback(int head, int row0, int t128, const uint8_t* sK, const uint8_t* sV) {
  const int row = row0 + (t128 >> 1), par = t128 & 1;
  __threadfence();
  float q[16];
  {
    const int rg = row >> 4, r = row & 15, sw = ((row >> 2) & 1) * 4;
    const float nm = __uint_as_float(__ldcg(&g_nrm[nrm_idx(0, head, rg)]).x);
    const bool cp = !(nm <= NRM_HI && nm >= NRM_LO);
    for (int c = 0; c < 16; c += 2) {
      if (cp) {
        uint32_t u = __ldcg((const uint32_t*)(g_qkb + (head * 128 + rg) * 32) + ((r & 7) * 4 + ((c & 7) >> 1)) * 4 + (r >> 3) + 2 * (c >> 3));
        q[c] = bflo(u); q[c + 1] = bfhi(u);
      } else {
        uint32_t u = __ldcg((const uint32_t*)(g_qkv + (head * S_ + row) * 2) + (((c & 7) + (c >> 3)) ^ sw));
        float2 f = __half22float2(*(__half2*)&u); q[c] = f.x; q[c + 1] = f.y;
      }
    }
  }
  float m = -INFINITY, l = 0.f, o[16];
#pragma unroll
  for (int d = 0; d < 16; d++) o[d] = 0.f;
  for (int key = par; key < S_; key += 2) {
    const int rg = key >> 4, r = key & 15, sw = ((key >> 2) & 1) * 4;
    const float nm = __uint_as_float(__ldcg(&g_nrm[nrm_idx(1, head, rg)]).x);
    const bool cp = !(nm <= NRM_HI && nm >= NRM_LO);
    float s = 0.f;
#pragma unroll
    for (int c = 0; c < 16; c += 2) {
      float k0, k1;
      if (cp) {
        uint32_t u = __ldcg((const uint32_t*)(g_qkb + ((H_ + head) * 128 + rg) * 32) + ((r & 7) * 4 + ((c & 7) >> 1)) * 4 + (r >> 3) + 2 * (c >> 3));
        k0 = bflo(u); k1 = bfhi(u);
      } else {
        uint32_t u = ((const uint32_t*)(sK + key * 32))[((c & 7) + (c >> 3)) ^ sw];
        float2 f = __half22float2(*(__half2*)&u); k0 = f.x; k1 = f.y;
      }
      s = fmaf(q[c], k0, s); s = fmaf(q[c + 1], k1, s);
    }
    const float mn = fmaxf(m, s);
    const float corr = exp2f(m - mn), p = exp2f(s - mn);
    const float pv = p * (((key & 63) < NMU) ? 1.f / VSC : 1.f / VSP);
    l = l * corr + p;
#pragma unroll
    for (int c = 0; c < 16; c += 2) {
      uint32_t u = ((const uint32_t*)(sV + key * 32))[((c & 7) + (c >> 3)) ^ sw];
      o[c] = fmaf(pv, bflo(u), o[c] * corr); o[c + 1] = fmaf(pv, bfhi(u), o[c + 1] * corr);
    }
    m = mn;
  }
  const float m2 = __shfl_xor_sync(~0u, m, 1), mm = fmaxf(m, m2), cf = exp2f(m - mm);
  l *= cf; l += __shfl_xor_sync(~0u, l, 1);
  const float inv = 1.f / l;
  uint32_t* dst = (uint32_t*)(g_o + (size_t)row * D_ + head * 16);
#pragma unroll
  for (int c = 0; c < 16; c += 2) {
    float a = o[c] * cf, b = o[c + 1] * cf;
    a += __shfl_xor_sync(~0u, a, 1); b += __shfl_xor_sync(~0u, b, 1);
    if (par == 0) dst[c >> 1] = packbf(a * inv, b * inv);
  }
}

constexpr uint32_t SM0 = 1024;
__host__ __device__ constexpr uint64_t cdesc(uint32_t off, uint32_t lbo, uint32_t sbo, uint32_t sw) {
  return (uint64_t)((SM0 + off) >> 4) | ((uint64_t)(lbo >> 4) << 16) | ((uint64_t)(sbo >> 4) << 32) | ((uint64_t)sw << 62);
}
constexpr uint32_t SM_ONES = 131072, SM_G = 132096, SM_BAR = 230400, SM_OK2 = SM_BAR + 372, SM_OK = SM_BAR + 376, SM_EP = SM_BAR + 380, SM_CS = SM_BAR + 384, SM_TOTAL = SM_CS + 1664;
constexpr uint32_t SM_RS = SM_ONES;
constexpr uint32_t GST = 32768, OST = 24576;
constexpr int B_QF = 0, B_QE = 8, B_ZF = 12, B_ZE = 15, B_ZG = 18, B_OF = 19, B_QD = 23, B_SF = 24, B_SE = 27, B_KV = 30, B_KVFREE = 38, B_CS = 39, B_OK = 40, B_PUB = 41, B_ST = 42,
              B_ATT = 43, B_T1 = 44, B_NUM = 45;
constexpr int B_OA = B_QF;

struct Params {
  CUtensorMap tmX, tmWq, tmWi, tmWsp, tmUst, tmU, tmWout, tmO, tmWo, tmSq, tmSi, tmOut;
  const bf16* x; const bf16* bsp; const bf16* wsp; const bf16* wqkv; const bf16* win; const bf16* wout; const bf16* wo; bf16* out;
  uint64_t segs[3];
};

__device__ __forceinline__ void att_segment(float* o, const uint32_t* q, int t0, int t1, uint32_t sm, float* f0, float* f1, uint32_t* h0, uint32_t* h1) {
  const uint64_t dK = mkdesc(sm, 16, 256, 3), dV = mkdesc(sm + 65536, 65536, 256, 3);
  uint32_t p0[16], p1[16];
  mbar_wait(sm + SM_BAR + (B_KV + t0) * 8, 0);
  wfence();
  uint64_t kb = dK + (uint64_t)t0 * 512, vb = dV + (uint64_t)t0 * (16 * INCV);
  att_qk(f0, h0, q, kb); wcommit();
  wwait<0>(); fence_regs<12>(f0); fence_regs<10>(h0);
  static_assert(B_KV + 8 == B_KVFREE, "the look-ahead wait of the last chunk lands on a completed barrier");
  const uint32_t bend = sm + SM_BAR + (B_KV + 1 + t1) * 8;
#pragma unroll 1
  for (uint32_t b = sm + SM_BAR + (B_KV + 1 + t0) * 8; b != bend; b += 8) {
    wfence();
    att_qk(f1, h1, q, kb + 128); wcommit();
    mbar_wait(b, 0);
    att_step(f0, h0, p0, o, q, vb, kb + 256, true);
    wwait<1>(); fence_regs<12>(f1); fence_regs<10>(h1);
    att_step(f1, h1, p1, o, q, vb + 4 * INCV, kb + 384, true);
    wwait<1>(); fence_regs<12>(f0); fence_regs<10>(h0);
    att_step(f0, h0, p0, o, q, vb + 8 * INCV, kb + 512, true);
    wwait<1>(); fence_regs<12>(f1); fence_regs<10>(h1);
    att_step(f1, h1, p1, o, q, vb + 12 * INCV, kb, false);
    wwait<1>(); fence_regs<12>(f0); fence_regs<10>(h0);
    kb = opaque(kb + 512); vb = opaque(vb + 16 * INCV);
  }
  wwait<0>(); fence_regs<12>(o);
}

__device__ __forceinline__ void att_exact(float* o, const uint32_t* q, uint32_t sm) {
  const uint64_t dK = mkdesc(sm, 16, 256, 3), dV = mkdesc(sm + 65536, 65536, 256, 3);
  float s[32], m0 = -INFINITY, m1 = -INFINITY;
#pragma unroll
  for (int i = 0; i < 32; i++) s[i] = 0.f;
#pragma unroll 1
  for (int it = 0; it < 64; it++) {
    fence_regs<32>(s);
    wfence();
    qk64(s, q, dK + (uint64_t)(it & 31) * 128); wcommit();
    wwait<0>(); fence_regs<32>(s);
    if (it < 32) {
#pragma unroll
      for (int j = 0; j < 8; j++) { m0 = fmaxf(m0, fmaxf(s[4 * j], s[4 * j + 1])); m1 = fmaxf(m1, fmaxf(s[4 * j + 2], s[4 * j + 3])); }
      if (it == 31) {
        m0 = fmaxf(m0, __shfl_xor_sync(~0u, m0, 1)); m0 = fmaxf(m0, __shfl_xor_sync(~0u, m0, 2));
        m1 = fmaxf(m1, __shfl_xor_sync(~0u, m1, 1)); m1 = fmaxf(m1, __shfl_xor_sync(~0u, m1, 2));
      }
    } else {
      uint32_t p[16];
#pragma unroll
      for (int j = 0; j < 8; j++) {
        const float c = j * 8 < NMU ? 1.f : VSC / VSP;
        p[2 * j] = packbf(ex2(s[4 * j] - m0) * c, ex2(s[4 * j + 1] - m0) * c);
        p[2 * j + 1] = packbf(ex2(s[4 * j + 2] - m1) * c, ex2(s[4 * j + 3] - m1) * c);
      }
      wfence();
#pragma unroll
      for (int j = 0; j < 4; j++) pv24(o, p + 4 * j, dV + (uint64_t)((it - 32) * 4 + j) * INCV + ((uint64_t)(j >= 2 ? 32 : j * 16) << 16));
      wcommit();
      wwait<0>(); fence_regs<12>(o);
    }
  }
}

__device__ __forceinline__ void sp_issue(const Params& P, uint32_t sm, int warp, int rb, int nt, int rank, int kb, int st, uint32_t eph) {
  const uint32_t fb = sm + SM_BAR + (B_SF + st) * 8, base = sm + SM_G + st * GST;
  if (warp == 1) {
    mbar_wait(sm + SM_BAR + (B_SE + st) * 8, eph);
    if (elect1()) bulk_ld_mc(base + 16384 + rank * 7168, g_z2t + (kb * FH_ + nt * 112 + rank * 56) * 8, 7168, fb);
  } else if (warp >= 2) {
    if (elect1()) {
      tma2d(base + (warp - 2) * 8192, &P.tmWsp, kb * 64, rb * 128 + (warp - 2) * 64, fb);
      if (warp == 2) mbar_expect(fb, 16384 + 14336);
    }
  }
}
__device__ __forceinline__ void z_issue(const Params& P, uint32_t sm, int nt, int rank, int m, int sl) {
  const uint32_t fb = sm + SM_BAR + (B_ZF + sl) * 8;
  tma2d_mc(sm + SM_G + sl * GST + rank * 16384, &P.tmWi, (m < 4 ? FH_ : 0) + nt * 112 + rank * 64, (m & 3) * 128, fb);
  mbar_expect(fb, GST);
}
__device__ __forceinline__ void wout_issue(const Params& P, uint32_t sm, int warp, int orow, int ocol, int kb) {
  const uint32_t fb = sm + SM_BAR + (B_OF + (kb & 3)) * 8, base = sm + SM_G + (kb & 3) * OST;
  if (warp > 0) {
    if (elect1()) {
      if (warp == 1) { tma2d(base, &P.tmU, kb * 64, orow, fb); mbar_expect(fb, OST); }
      else tma2d(base + (warp - 1) * 8192, &P.tmWout, ocol + (warp - 2) * 64, kb * 64, fb);
    }
  }
}
__host__ __device__ constexpr uint32_t wo_b(int kb) { return kb < 6 ? SM_G + kb * 16384 : 65536 + (kb - 6) * 16384; }

__device__ __forceinline__ void pa_x(const Params& P, uint32_t sm, int kb, int rb) {
  const uint32_t fb = sm + SM_BAR + (B_QF + kb) * 8;
  tma2d(sm + kb * 16384, &P.tmX, kb * 64, rb * 128, fb);
  tma2d(sm + kb * 16384 + 8192, &P.tmX, kb * 64, rb * 128 + 64, fb);
  mbar_expect(fb, 40960);
}
__device__ __forceinline__ void pa_w(const Params& P, uint32_t sm, int kb, int nt, int rank) {
  const uint32_t fb = sm + SM_BAR + (B_QF + kb) * 8, base = sm + SM_G + (kb & 3) * OST;
  const int box = (rank + kb) & 1;
  tma2d_mc(base + box * 8192, &P.tmWq, box * 512 + nt * 64, kb * 64, fb);
  if (box == 0) tma2d_mc(base + 16384, &P.tmWq, 1024 + nt * 64, kb * 64, fb);
}

__device__ __forceinline__ void sp_prefetch(const Params& P, int w, int rb, int nt) {
#pragma unroll
  for (int i = 0; i < 2; i++)
    asm volatile("cp.async.bulk.prefetch.tensor.2d.L2.global [%0, {%1, %2}];" ::"l"(&P.tmWsp), "r"((w * 8 + nt) * 64), "r"(rb * 128 + i * 64) : "memory");
}
__global__ void __launch_bounds__(512, 1) k_mega(const __grid_constant__ Params P) {
  extern __shared__ __align__(1024) uint8_t smp[];
  const uint32_t sm = s2u(smp);
  const int tid = threadIdx.x, lane = tid & 31;
  const int warp = __shfl_sync(~0u, (tid >> 5) & 3, 0);
  const int wg = __shfl_sync(~0u, tid >> 7, 0);
  const int bid = blockIdx.x, rank = bid & 1, rb = ((bid >> 1) & 7) * 2 + rank, nt = (bid >> 4) & 7;
  if ((sm & 0xFFFFFFu) != SM0) __trap();
  const uint32_t bar = sm + SM_BAR;
  unsigned ticket = 0;
  if (wg == 0) {
    if (elect1()) {
#pragma unroll
      for (int w = 0; w < 4; w++)
        if (warp == w) {
#pragma unroll
          for (int i = w * 12; i < (w * 12 + 12 < B_NUM ? w * 12 + 12 : B_NUM); i++)
            mbar_init(bar + i * 8, (i >= B_QE && i < B_ZF) || (i >= B_ZE && i < B_ZG) ? 4 : i == B_KVFREE || i == B_QD ? 8 : i == B_CS ? 256 : i == B_ATT ? 12 : i == B_T1 ? 24 : 1);
        }
      asm volatile("fence.mbarrier_init.release.cluster;" ::: "memory");
      if (warp == 0 && bid < 128) pa_x(P, sm, 0, rb);
    }
  } else if (tid == 256) {
    asm volatile("atom.relaxed.gpu.global.add.u32 %0, [%1], 1;" : "=r"(ticket) : "l"(&g_cnt[C_TICKET * 8]) : "memory");
  } else if (tid >= 128 && tid < 140) {
    asm volatile("prefetch.tensormap [%0];" ::"l"(&P.tmX + (tid - 128)) : "memory");
  }
  asm volatile("barrier.cluster.arrive.relaxed.aligned; barrier.cluster.wait.aligned;" ::: "memory");
  const int g = lane >> 2, t = lane & 3;
  const int head = ((bid >> 1) & 7) + (bid >> 5) * 8, quarter = ((bid >> 4) & 1) * 2 + rank, h = wg & 1;
  uint32_t tag;
  float2 rsa, rsb;

  if (bid >= 128) {
    const int hd0 = (bid - 128) * 8;
    if (tid == 256) *(volatile unsigned*)(smp + SM_EP) = ticket / gridDim.x;
    if (tid < 64) { const uint32_t ov = tid < 32 ? 0x3FB53FB5u : 0x33003300u; ((uint4*)(smp + SM_ONES))[tid] = make_uint4(ov, ov, ov, ov); fence_async_smem(); }
    __syncthreads();
    tag = *(volatile unsigned*)(smp + SM_EP) + 1;
    auto hload = [&](int j, uint32_t b) {
      mbar_expect(b, 32768);
      bulk_ld(sm + (j & 3) * 16384, g_qkv + ((H_ + hd0 + j) * S_) * 2, 16384, b);
      bulk_ld(sm + 65536 + (j & 3) * 16384, g_qkv + ((2 * H_ + hd0 + j) * S_) * 2, 16384, b);
    };
    if (tid == 0) {
      cnt_wait(C_QKV + (hd0 >> 2), tag * 16);
      cnt_wait(C_QKV + (hd0 >> 2) + 1, tag * 16);
#pragma unroll 1
      for (int j = 0; j < 4; j++) hload(j, bar + (B_QF + j) * 8);
#pragma unroll 1
      for (int i = 0; i < 8; i++) { mbar_arrive(bar + (B_KV + i) * 8); mbar_arrive(bar + B_KVFREE * 8); }
    }
    __syncthreads();
    float f0[12], f1[12]; uint32_t h0[10], h1[10];
#pragma unroll
    for (int i = 0; i < 12; i++) { f0[i] = 0.f; f1[i] = 0.f; }
#pragma unroll
    for (int i = 0; i < 10; i++) { h0[i] = 0; h1[i] = 0; }
    fence_regs<12>(f0); fence_regs<12>(f1); fence_regs<10>(h0); fence_regs<10>(h1);
    const uint32_t* qp = (const uint32_t*)(g_qkv + (hd0 * S_ + wg * 512 + 448 + warp * 16 + g) * 2);
    const int sw = ((g >> 2) & 1) * 4;
    uint32_t qn[4] = {__ldcg(qp + (t ^ sw)), __ldcg(qp + 64 + (t ^ sw)), __ldcg(qp + ((t + 4) ^ sw)), __ldcg(qp + 64 + ((t + 4) ^ sw))};
#pragma unroll 1
    for (int j = 0; j < 8; j++) {
      uint32_t q[4] = {qn[0], qn[1], qn[2], qn[3]};
      fence_regs<4>(q);
      qp += (j < 7) * S_ * 8;
      qn[0] = __ldcg(qp + (t ^ sw)); qn[1] = __ldcg(qp + 64 + (t ^ sw)); qn[2] = __ldcg(qp + ((t + 4) ^ sw)); qn[3] = __ldcg(qp + 64 + ((t + 4) ^ sw));
      float o[12];
#pragma unroll
      for (int i = 0; i < 12; i++) o[i] = 0.f;
      fence_regs<12>(o);
      mbar_wait(bar + (B_QF + j) * 8, 0);
      att_segment(o, q, (j & 3) * 2, (j & 3) * 2 + 2, sm, f0, f1, h0, h1);
      uint4* hp = g_hp + ((hd0 + j) * 4 + wg) * 5 * 128 + (tid & 127);
#pragma unroll
      for (int i = 0; i < 4; i++) put2(hp + i * 128, o[2 * i], o[2 * i + 1], tag);
      put2(hp + 512, o[8], o[10], tag);
      if (j < 4) {
        nbar(2 + wg, 128);
        if ((tid & 127) == 0) mbar_arrive(bar + (B_QE + j) * 8);
        if (wg == j && warp == 1) { mbar_wait(bar + (B_QE + j) * 8, 0); if (elect1()) hload(j + 4, bar + (B_QF + j + 4) * 8); }
      }
      nbar(2 + wg, 128);
    }
    return;
  }

  if (wg >= 2) {
    const int w8 = (tid >> 5) - 8, tt = tid - 256;
    uint4 xa[4];
    {
      const uint4* p = (const uint4*)(P.x + (size_t)(rb * 128 + nt * 16 + w8 * 2) * D_) + lane;
#pragma unroll
      for (int i = 0; i < 4; i++) xa[i] = __ldg(p + i * 32);
    }
    if (w8 == 7) {
      if (elect1()) {
#pragma unroll 1
        for (int i = 1; i < (bid < 104 ? 6 : 8); i++) {
          pa_x(P, sm, i, rb);
          if (i < 4) pa_w(P, sm, i, nt, rank);
          if (i == STRIPAT && bid < 104) {
            const CUtensorMap* m = bid < 48 ? &P.tmSq : &P.tmSi;
            const int col = (bid < 48 ? bid : bid - 48) * 32;
            mbar_expect(bar + B_ST * 8, 32768);
            tma2d(sm + 98304, m, col, 0, bar + B_ST * 8);
            tma2d(sm + 98304 + 16384, m, col, 256, bar + B_ST * 8);
          }
        }
      }
      __syncwarp();
    }
    if (tid == 256) *(volatile unsigned*)(smp + SM_EP) = ticket / gridDim.x;
    nbar(8, 256);
    tag = *(volatile unsigned*)(smp + SM_EP) + 1;
    {
      float ra = 0.f, rc = 0.f;
#pragma unroll
      for (int r = 0; r < 2; r++) {
        const uint32_t w[8] = {xa[2 * r].x, xa[2 * r].y, xa[2 * r].z, xa[2 * r].w, xa[2 * r + 1].x, xa[2 * r + 1].y, xa[2 * r + 1].z, xa[2 * r + 1].w};
        float v[16], s = 0.f;
#pragma unroll
        for (int i = 0; i < 8; i++) { v[2 * i] = bflo(w[i]); v[2 * i + 1] = bfhi(w[i]); s += v[2 * i] + v[2 * i + 1]; }
#pragma unroll
        for (int o = 16; o; o >>= 1) s += __shfl_xor_sync(~0u, s, o);
        const float m = s * (1.f / D_);
        float q = 0.f;
#pragma unroll
        for (int i = 0; i < 16; i++) { v[i] -= m; q = fmaf(v[i], v[i], q); }
#pragma unroll
        for (int o = 16; o; o >>= 1) q += __shfl_xor_sync(~0u, q, o);
        if (lane == r) { ra = m; rc = q * (1.f / D_); }
      }
      const float2 lc = ln_coef(ra, rc);
      if (lane < 2) put2(&g_rs[rb * 128 + nt * 16 + w8 * 2 + lane], lc.x, lc.y, tag);
    }
    if (bid < 104) {
      mbar_wait(bar + B_ST * 8, 0);
      float cs[8];
#pragma unroll
      for (int j = 0; j < 8; j++) cs[j] = 0.f;
#pragma unroll
      for (int i = 0; i < 8; i++) {
        const uint4 w = *(const uint4*)(smp + 98304 + i * 4096 + tt * 16);
        cs[0] += bflo(w.x); cs[1] += bfhi(w.x); cs[2] += bflo(w.y); cs[3] += bfhi(w.y);
        cs[4] += bflo(w.z); cs[5] += bfhi(w.z); cs[6] += bflo(w.w); cs[7] += bfhi(w.w);
      }
#pragma unroll
      for (int j = 0; j < 8; j++) { cs[j] += __shfl_xor_sync(~0u, cs[j], 4); cs[j] += __shfl_xor_sync(~0u, cs[j], 8); cs[j] += __shfl_xor_sync(~0u, cs[j], 16); }
      float* red = (float*)(smp + SM_RS);
      if (lane < 4) {
        *(float4*)&red[w8 * 32 + lane * 8] = make_float4(cs[0], cs[1], cs[2], cs[3]);
        *(float4*)&red[w8 * 32 + lane * 8 + 4] = make_float4(cs[4], cs[5], cs[6], cs[7]);
      }
      fence_async_smem();
      nbar(8, 256);
      if (w8 == 7) {
        if (elect1()) { pa_x(P, sm, 6, rb); pa_x(P, sm, 7, rb); }
      } else if (w8 == 2 && lane < 16) {
        float a = 0.f, b = 0.f;
#pragma unroll
        for (int w = 0; w < 8; w++) { const float2 v = *(const float2*)&red[w * 32 + lane * 2]; a += v.x; b += v.y; }
        put2(&g_cs[bid * 16 + lane], a, b, tag);
      }
      nbar(8, 256);
    }
    {
      const uint4* gap = &g_cs[tt < 96 ? (tt >> 5) * 256 + nt * 32 + (tt & 31) : tt < 152 ? 768 + nt * 56 + tt - 96 : 1216 + nt * 56 + (tt < 208 ? tt - 152 : 0)];
      const uint4* gbp = &g_rs[rb * 128 + (tt & 127)];
      uint4 ga, gb;
#pragma unroll 1
      for (int it = 0; it < (1 << 16); it++) {
        ga = ldv4(gap); gb = ldv4(gbp);
        if (__all_sync(~0u, ga.y == tag && ga.w == tag && gb.y == tag && gb.w == tag)) break;
        __nanosleep(100);
      }
      if (tt < 208) ((float2*)(smp + SM_CS))[tt] = make_float2(__uint_as_float(ga.x), __uint_as_float(ga.z));
      if (tt < 128) ((float2*)(smp + SM_RS))[tt] = make_float2(__uint_as_float(gb.x), __uint_as_float(gb.z));
      mbar_arrive(bar + B_CS * 8);
    }
    if (w8 == 7) { if (elect1()) sp_prefetch(P, 0, rb, nt); }
    mbar_wait(bar + B_CS * 8, 0);
    rsa = lds2(sm + SM_RS + (h * 64 + warp * 16 + g) * 8); rsb = lds2(sm + SM_RS + (h * 64 + warp * 16 + 8 + g) * 8);
    if (wg == 3 && warp == 2) {
      mbar_wait(bar + (B_QF + 5) * 8, 0);
      mbar_wait(bar + B_QE * 8, 1);
      mbar_wait(bar + (B_QE + 1) * 8, 1);
      if (elect1()) z_issue(P, sm, nt, rank, 0, 0);
      mbar_wait(bar + (B_QF + 6) * 8, 0);
      mbar_wait(bar + (B_QE + 2) * 8, 1);
      if (elect1()) z_issue(P, sm, nt, rank, 1, 1);
    }
  } else {
    if (wg == 0) { if (warp == 1) { if (elect1()) pa_w(P, sm, 0, nt, rank); } }
    else if (warp == 0) {
      if (elect1()) {
#pragma unroll
        for (int i = 0; i < 8; i++) mbar_expect(bar + (B_KV + i) * 8, 16384);
      }
    }
    float aq[96];
#pragma unroll
    for (int i = 0; i < 96; i++) aq[i] = 0.f;
    fence_regs<96>(aq);
#pragma unroll 1
    for (int kb = 0; kb < 8; kb++) {
      mbar_wait(bar + (B_QF + kb) * 8, 0);
      const uint64_t da = opaque(cdesc(0, 16, 1024, 1) + (kb * 1024 + wg * 512)), dq = opaque(cdesc(SM_G, 8192, 1024, 1) + (kb & 3) * (OST >> 4));
      wfence();
#pragma unroll
      for (int k = 0; k < 4; k++) mm192t(aq, da + k * 2, dq + k * 128, 1);
      wcommit();
      wwait<1>();
      if (kb > 0 && warp < 2) {
        const uint32_t eb = bar + (B_QE + ((kb - 1) & 3)) * 8;
        if (elect1()) { if (warp == 0) mbar_arrive(eb); else mbar_arrive_peer(eb, rank); }
      }
      if (kb >= 2 && kb <= 5 && warp == 3 && (kb & 1) == wg) {
        mbar_wait(bar + (B_QE + kb - 2) * 8, 0);
        if (elect1()) pa_w(P, sm, kb + 2, nt, rank);
      }
    }
    const int rg = rb * 8 + wg * 4 + warp;
    mbar_wait(bar + B_CS * 8, 0);
    tag = *(volatile unsigned*)(smp + SM_EP) + 1;
    rsa = lds2(sm + SM_RS + (wg * 64 + warp * 16 + g) * 8); rsb = lds2(sm + SM_RS + (wg * 64 + warp * 16 + 8 + g) * 8);
    wwait<0>();
    fence_regs<96>(aq);
    if (warp < 2) { if (elect1()) { if (warp == 0) mbar_arrive(bar + (B_QE + 3) * 8); else mbar_arrive_peer(bar + (B_QE + 3) * 8, rank); } }
    uint2* qkvp = (uint2*)(g_qkv + (nt * 4 * S_ + rg * 16 + g) * 2) + (t ^ (((g >> 2) & 1) * 2));
    const float2* csp = (const float2*)(smp + SM_CS) + t;
#pragma unroll
    for (int ty = 0; ty < 3; ty++) {
      const float sa = ty == 0 ? QSCALE : ty == 1 ? 1.f : (warp * 16 < NMU ? VSC : VSP), sb = ty < 2 ? sa : (warp * 16 + 8 < NMU ? VSC : VSP);
      const float r0 = rsa.x * sa, c0 = rsa.y * sa, r1 = rsb.x * sb, c1 = rsb.y * sb;
#pragma unroll
      for (int jj = 0; jj < 4; jj++) {
        const int j = ty * 4 + jj;
        float* a = aq + j * 8;
        const float2 ca = csp[j * 8], cb = csp[j * 8 + 4];
        a[0] = fmaf(a[0], r0, c0 * ca.x); a[1] = fmaf(a[1], r0, c0 * ca.y); a[2] = fmaf(a[2], r1, c1 * ca.x); a[3] = fmaf(a[3], r1, c1 * ca.y);
        a[4] = fmaf(a[4], r0, c0 * cb.x); a[5] = fmaf(a[5], r0, c0 * cb.y); a[6] = fmaf(a[6], r1, c1 * cb.x); a[7] = fmaf(a[7], r1, c1 * cb.y);
        uint2* dst = qkvp + (ty * H_ + jj) * S_ * 4;
        if (ty == 2) { dst[0] = make_uint2(packbf(a[0], a[1]), packbf(a[4], a[5])); dst[32] = make_uint2(packbf(a[2], a[3]), packbf(a[6], a[7])); }
        else { dst[0] = make_uint2(packh(a[0], a[1]), packh(a[4], a[5])); dst[32] = make_uint2(packh(a[2], a[3]), packh(a[6], a[7])); }
      }
    }
    uint32_t mx[8];
#pragma unroll
    for (int j = 0; j < 8; j++) {
      const float* a = aq + j * 8;
      float n0 = a[0] * a[0] + a[1] * a[1] + a[4] * a[4] + a[5] * a[5];
      float n1 = a[2] * a[2] + a[3] * a[3] + a[6] * a[6] + a[7] * a[7];
      n0 += __shfl_xor_sync(~0u, n0, 1); n1 += __shfl_xor_sync(~0u, n1, 1);
      n0 += __shfl_xor_sync(~0u, n0, 2); n1 += __shfl_xor_sync(~0u, n1, 2);
      mx[j] = __reduce_max_sync(~0u, max(__float_as_uint(n0) & 0x7fffffffu, __float_as_uint(n1) & 0x7fffffffu));
    }
    uint32_t lo = mx[0], hi = mx[0], mine = mx[0];
#pragma unroll
    for (int j = 1; j < 8; j++) { lo = min(lo, mx[j]); hi = max(hi, mx[j]); if (lane == j) mine = mx[j]; }
    if (!(__uint_as_float(hi) <= NRM_HI && __uint_as_float(lo) >= NRM_LO)) {
#pragma unroll
      for (int j = 0; j < 8; j++) {
        const float* a = aq + j * 8;
        g_qkb[(((j >> 2) * H_ + nt * 4 + (j & 3)) * 128 + rg) * 32 + lane] = make_uint4(packbf(a[0], a[1]), packbf(a[2], a[3]), packbf(a[4], a[5]), packbf(a[6], a[7]));
      }
      __threadfence();
      __syncwarp();
    }
    if (lane < 8)
      asm volatile("st.relaxed.gpu.global.v2.u32 [%0], {%1,%2};" ::"l"(&g_nrm[(nt * 128 + rg) * 8 + lane]), "r"(mine), "r"(tag) : "memory");
    __syncwarp();
    if (lane == 0) mbar_arrive(bar + B_QD * 8);
    nbar(2 + wg, 128);
  }

  {
    const int zt = wg < 2;
    float acc[56];
#pragma unroll
    for (int i = 0; i < 56; i++) acc[i] = 0.f;
    fence_regs<56>(acc);
    if (zt) mbar_wait(bar + B_ZG * 8, 0);
#pragma unroll 1
    for (int kb = 0, sl = zt, ph = zt; kb < 4; kb++) {
      const int n = zt * 4 + kb;
      mbar_wait(bar + (B_ZF + sl) * 8, ph);
      const uint64_t da = opaque(cdesc(0, 16, 1024, 1) + (kb * 2048 + h * 512)), db = opaque(cdesc(SM_G, 16384, 1024, 1) + sl * 2048);
      wfence();
#pragma unroll
      for (int k = 0; k < 8; k++) mm112t(acc, da + (k >> 2) * 1024 + (k & 3) * 2, db + k * 128, 1);
      wcommit();
      wwait<1>();
      int ps = sl == 0 ? 2 : sl - 1;
      if (n == 4) { wwait<0>(); ps = sl; }
      if (n >= 1 && n <= 4 && warp < 2) {
        if (elect1()) { if (warp == 0) mbar_arrive(bar + (B_ZE + ps) * 8); else mbar_arrive_peer(bar + (B_ZE + ps) * 8, rank); }
      }
      if (n >= 1 && n <= 3 && warp == 3 && (n & 1) == h) {
        mbar_wait(bar + (B_ZE + ps) * 8, 0);
        if (elect1()) { z_issue(P, sm, nt, rank, n + 2, ps); if (n == 2) mbar_arrive(bar + B_ZG * 8); }
      }
      if (n == 0 && wg == 2 && warp == 2) {
        mbar_wait(bar + (B_QF + 7) * 8, 0);
        mbar_wait(bar + (B_QE + 2) * 8, 1);
        mbar_wait(bar + (B_QE + 3) * 8, 1);
        if (elect1()) z_issue(P, sm, nt, rank, 2, 2);
      }
      if (++sl == 3) { sl = 0; ph ^= 1; }
    }
    wwait<0>();
    fence_regs<56>(acc);
    if (warp < 2) {
      if (elect1()) {
        if (warp == 0) { mbar_arrive(bar + B_KVFREE * 8); if (!zt) mbar_arrive(bar + B_ZE * 8); }
        else { mbar_arrive_peer(bar + B_KVFREE * 8, rank); if (!zt) mbar_arrive_peer(bar + B_ZE * 8, rank); }
      }
    }
    if (!zt) {
      if (warp == 3) {
        mbar_wait(bar + (B_ZE + h) * 8, 1);
        if (elect1()) z_issue(P, sm, nt, rank, 6 + h, h);
      } else if (warp == 1 && h == 0) {
        mbar_wait(bar + B_QD * 8, 0);
        if (elect1()) cnt_add_rel(C_QKV + nt);
      }
      if (wg == 2 && warp == 2) {
        const uint2* kp = &g_nrm[nrm_idx(1, head, lane)];
        const uint2* qp = &g_nrm[nrm_idx(0, head, quarter * 32 + lane)];
        uint2 v[5];
#pragma unroll 1
        for (int it = 0; it < (1 << 16); it++) {
          bool ok = true;
#pragma unroll
          for (int i = 0; i < 5; i++)
            asm volatile("ld.relaxed.gpu.global.v2.u32 {%0,%1}, [%2];" : "=r"(v[i].x), "=r"(v[i].y) : "l"(i < 4 ? kp + i * 256 : qp) : "memory");
#pragma unroll
          for (int i = 0; i < 5; i++) ok = ok && v[i].y == tag;
          if (__all_sync(~0u, ok)) break;
          __nanosleep(100);
        }
        const float qn = __uint_as_float(v[4].x);
        const float kn = __uint_as_float(__reduce_max_sync(~0u, max(max(v[0].x, v[1].x), max(v[2].x, v[3].x))));
        const uint32_t okm = __ballot_sync(~0u, (qn * kn <= 6400.f) && (qn <= NRM_HI) && (kn <= NRM_HI));
        const uint32_t ok2 = __ballot_sync(~0u, (qn <= NRM_HI) && (kn <= NRM_HI));
        mbar_wait(bar + B_ZE * 8, 1);
        mbar_wait(bar + (B_ZE + 1) * 8, 1);
        const uint32_t ov = lane < 16 ? 0x3FB53FB5u : 0x33003300u;
        ((uint4*)(smp + SM_ONES))[lane * 2] = make_uint4(ov, ov, ov, ov);
        ((uint4*)(smp + SM_ONES))[lane * 2 + 1] = make_uint4(ov, ov, ov, ov);
        fence_async_smem();
        __syncwarp();
        if (lane == 0) { *(volatile uint32_t*)(smp + SM_OK) = okm; *(volatile uint32_t*)(smp + SM_OK2) = ok2; mbar_arrive(bar + B_OK * 8); }
        __syncwarp();
      }
    }
    const int row0 = rb * 128 + h * 64 + warp * 16 + g;
    const float2* csp = (const float2*)(smp + SM_CS) + 152 - zt * 56 + t;
    rsa.x *= 0.5f; rsa.y *= 0.5f; rsb.x *= 0.5f; rsb.y *= 0.5f;
#pragma unroll
    for (int j = 0; j < 14; j++) {
      float* a = acc + j * 4;
      const float2 cv = csp[j * 4];
      a[0] = gelu_half(fmaf(a[0], rsa.x, rsa.y * cv.x)); a[1] = gelu_half(fmaf(a[1], rsa.x, rsa.y * cv.y));
      a[2] = gelu_half(fmaf(a[2], rsb.x, rsb.y * cv.x)); a[3] = gelu_half(fmaf(a[3], rsb.x, rsb.y * cv.y));
    }
    if (zt) {
      uint4* z1p = g_z1 + ((rb * 8 + h * 4 + warp) * 56 + nt * 7) * 32 + lane;
#pragma unroll
      for (int j = 0; j < 7; j++) {
        const float* a = acc + j * 8;
        z1p[j * 32] = make_uint4(packbf(a[0], a[1]), packbf(a[2], a[3]), packbf(a[4], a[5]), packbf(a[6], a[7]));
      }
      nbar_arrive(9, 384);
    } else {
      float s0 = 0.f, s1 = 0.f, q0 = 0.f, q1 = 0.f;
#pragma unroll
      for (int j = 0; j < 14; j++) {
        const float* a = acc + j * 4;
        s0 += a[0] + a[1]; s1 += a[2] + a[3];
        q0 = fmaf(a[0], a[0], q0); q0 = fmaf(a[1], a[1], q0); q1 = fmaf(a[2], a[2], q1); q1 = fmaf(a[3], a[3], q1);
      }
#pragma unroll
      for (int o = 1; o <= 2; o <<= 1) {
        s0 += __shfl_xor_sync(~0u, s0, o); s1 += __shfl_xor_sync(~0u, s1, o);
        q0 += __shfl_xor_sync(~0u, q0, o); q1 += __shfl_xor_sync(~0u, q1, o);
      }
      if (t < 2) put2(&g_stat[nt * S_ + row0 + t * 8], t ? s1 : s0, t ? q1 : q0, tag);
      if (wg == 3 && warp == 2) {
        if (elect1()) { cnt_wait(C_QKV + (head >> 2), tag * 16); mbar_arrive(bar + B_PUB * 8); }
        __syncwarp();
        mbar_wait(bar + B_KVFREE * 8, 0);
        if (elect1()) {
#pragma unroll
          for (int i = 0; i < 8; i++) {
            constexpr int order[8] = {0, SPLA, 1, SPLA == 7 ? 5 : 7, 2, 3, 4, SPLA == 7 ? 6 : 11 - SPLA};
            const int ch = order[i];
            bulk_ld_mc(sm + rank * 65536 + ch * 8192, g_qkv + (((1 + rank) * H_ + head) * S_ + ch * 256) * 2, 8192, bar + (B_KV + ch) * 8);
          }
        }
        __syncwarp();
      }
      const uint4* sp = &g_stat[(t >> 1) * 4 * S_ + row0 + (t & 1) * 8];
      uint4 u[4];
#pragma unroll 1
      for (int it = 0; it < (1 << 16); it++) {
#pragma unroll
        for (int i = 0; i < 4; i++) u[i] = ldv4(sp + i * S_);
        bool ok = true;
#pragma unroll
        for (int i = 0; i < 4; i++) ok = ok && u[i].y == tag && u[i].w == tag;
        if (__all_sync(~0u, ok)) break;
        __nanosleep(64);
      }
      float sum = (__uint_as_float(u[0].x) + __uint_as_float(u[1].x)) + (__uint_as_float(u[2].x) + __uint_as_float(u[3].x));
      float sq = (__uint_as_float(u[0].z) + __uint_as_float(u[1].z)) + (__uint_as_float(u[2].z) + __uint_as_float(u[3].z));
      sum += __shfl_xor_sync(~0u, sum, 2); sq += __shfl_xor_sync(~0u, sq, 2);
      const float mean = sum * (1.f / FH_);
      const float2 lc = ln_coef(mean, fmaxf(sq * (1.f / FH_) - mean * mean, 0.f));
      const float zr = lc.x, zc = lc.y;
      const float r0 = __shfl_sync(~0u, zr, lane & ~3), c0 = __shfl_sync(~0u, zc, lane & ~3);
      const float r1 = __shfl_sync(~0u, zr, (lane & ~3) + 1), c1 = __shfl_sync(~0u, zc, (lane & ~3) + 1);
      mbar_wait(bar + B_KVFREE * 8, 0);
      const uint32_t stg = sm + SM_G + 2 * GST + h * 14336;
      const uint32_t sa = stg + ((lane >> 4) * 8 + (lane & 7)) * 128 + (((warp * 2 + ((lane >> 3) & 1)) ^ (lane & 7)) << 4);
#pragma unroll
      for (int j = 0; j < 7; j++) {
        const float* a = acc + j * 8;
        stsm4t(sa + j * 2048, packbf(fmaf(a[0], r0, c0), fmaf(a[1], r0, c0)), packbf(fmaf(a[2], r1, c1), fmaf(a[3], r1, c1)),
               packbf(fmaf(a[4], r0, c0), fmaf(a[5], r0, c0)), packbf(fmaf(a[6], r1, c1), fmaf(a[7], r1, c1)));
      }
      fence_async_smem();
      if (wg == 2) nbar_arrive(8, 256); else nbar(8, 256);
    }
  }

  if (wg == 3) {
    if (warp == 0) {
      if (elect1()) {
        bulk_st(g_z2t + ((rb * 2) * FH_ + nt * 112) * 8, sm + SM_G + 2 * GST, 14336);
        bulk_st(g_z2t + ((rb * 2 + 1) * FH_ + nt * 112) * 8, sm + SM_G + 2 * GST + 14336, 14336);
        bulk_commit(); bulk_wait0();
        cnt_add_rlx(C_Z2 + nt);
#pragma unroll
        for (int i = 0; i < 3; i++) mbar_arrive_peer(bar + (B_SE + i) * 8, rank);
      }
    } else if (warp == 1) {
      if (elect1()) cnt_wait(C_Z2 + nt, tag * 16);
    } else {
      sp_issue(P, sm, warp, rb, nt, rank, 0, 0, 0); sp_issue(P, sm, warp, rb, nt, rank, 1, 1, 0);
    }
    nbar(9, 384);
    if (warp == 1) { sp_issue(P, sm, warp, rb, nt, rank, 0, 0, 0); sp_issue(P, sm, warp, rb, nt, rank, 1, 1, 0); }
    asm volatile("setmaxnreg.inc.sync.aligned.u32 152;");
    float acc[112];
#pragma unroll
    for (int i = 0; i < 112; i++) acc[i] = 0.f;
    fence_regs<112>(acc);
#pragma unroll 1
    for (int kb = 0, st = 0, ph = 0; kb < 32; kb++) {
      mbar_wait(bar + (B_SF + st) * 8, ph);
      const uint64_t da = opaque(cdesc(SM_G, 16, 1024, 1) + st * (GST >> 4)), db = da + 1024;
      wfence();
#pragma unroll
      for (int k = 0; k < 4; k++) { mm112(acc, da + k * 2, db + k * 2, 1); mm112(acc + 56, da + 512 + k * 2, db + k * 2, 1); }
      wcommit();
      wwait<1>();
      if (kb + 2 < 32) {
        const int pst = st == 0 ? 2 : st - 1;
        if (warp == 0) {
          if (elect1()) {
            if (kb > 0) mbar_arrive_peer(bar + (B_SE + pst) * 8, rank);
            if ((kb & 7) == 0) {
              if (kb < 24) sp_prefetch(P, (kb >> 3) + 1, rb, nt);
              else { l2_prefetch(P.wout + (size_t)bid * 3584, 7168); l2_prefetch(P.wo + (size_t)bid * 2048, 4096); }
            }
          }
        }
        sp_issue(P, sm, warp, rb, nt, rank, kb + 2, pst, st == 0 ? ph : ph ^ 1);
      }
      if (++st == 3) { st = 0; ph ^= 1; }
    }
    wwait<0>();
    fence_regs<112>(acc);
    const int orow = rb * 128 + (nt >> 2) * 64, ocol = (nt & 3) * 128;
    if (warp >= 2) { wout_issue(P, sm, warp, orow, ocol, 0); wout_issue(P, sm, warp, orow, ocol, 1); }
    {
      const uint4* z1p = g_z1 + ((rb * 8 + warp) * 56 + nt * 7) * 32 + lane;
      const uint32_t stg = sm + SM_G + 2 * GST;
      const uint32_t sa = stg + (warp * 16 + ((lane >> 3) & 1) * 8 + (lane & 7)) * 224 + (lane >> 4) * 16;
      const float bs = __bfloat162float(P.bsp[rb * 128 + (t >> 1) * 64 + warp * 16 + (t & 1) * 8 + g]);
#pragma unroll 1
      for (int h = 0; h < 2; h++) {
        const float b0 = __shfl_sync(~0u, bs, (lane & ~3) + 2 * h), b1 = __shfl_sync(~0u, bs, (lane & ~3) + 2 * h + 1);
#pragma unroll
        for (int j = 0; j < 7; j++) {
          float* a = acc + j * 8;
          const uint4 z = __ldcg(&z1p[(h * 4 * 56 + j) * 32]);
          stsm4(sa + h * 14336 + j * 32, packbf(bflo(z.x) * (a[0] + b0), bfhi(z.x) * (a[1] + b0)), packbf(bflo(z.y) * (a[2] + b1), bfhi(z.y) * (a[3] + b1)),
                packbf(bflo(z.z) * (a[4] + b0), bfhi(z.z) * (a[5] + b0)), packbf(bflo(z.w) * (a[6] + b1), bfhi(z.w) * (a[7] + b1)));
        }
#pragma unroll
        for (int i = 0; i < 56; i++) acc[i] = acc[56 + i];
      }
      fence_async_smem();
      nbar(5, 128);
      if (warp == 1) {
        if (elect1()) { tma2d_st(&P.tmUst, stg, nt * 112, rb * 128); bulk_commit(); bulk_wait0(); cnt_add_rlx(C_U + rb); cnt_wait(C_U + rb, tag * 8);
#pragma unroll 1
          for (int kb = 0; kb < 3; kb++) { tma2d(sm + SM_G + kb * OST, &P.tmU, kb * 64, orow, bar + (B_OF + kb) * 8); mbar_expect(bar + (B_OF + kb) * 8, OST); }
        }
      }
      nbar(5, 128);
    }
    if (warp >= 2) wout_issue(P, sm, warp, orow, ocol, 2);
#pragma unroll
    for (int i = 0; i < 64; i++) acc[i] = 0.f;
    fence_regs<64>(acc);
#pragma unroll 1
    for (int kb = 0; kb < 14; kb++) {
      mbar_wait(bar + (B_OF + (kb & 3)) * 8, (kb >> 2) & 1);
      const uint64_t da = opaque(cdesc(SM_G, 16, 1024, 1) + (kb & 3) * (OST >> 4)), db = da + (cdesc(SM_G + 8192, 8192, 1024, 1) - cdesc(SM_G, 16, 1024, 1));
      wfence();
#pragma unroll
      for (int k = 0; k < 4; k++) mm128t(acc, da + k * 2, db + k * 128, 1);
      wcommit();
      wwait<1>();
      if (kb + 3 < 14) wout_issue(P, sm, warp, orow, ocol, kb + 3);
    }
    wwait<0>();
    fence_regs<64>(acc);
    if (warp >= 2) {
      if (elect1()) {
#pragma unroll 1
        for (int kb = 0; kb < 6; kb++) tma2d(sm + SM_G + kb * 16384 + (warp - 2) * 8192, &P.tmWo, ocol + (warp - 2) * 64, kb * 64, bar + (B_OA + kb) * 8);
      }
    } else if (warp == 1) {
      if (elect1()) {
#pragma unroll
        for (int kb = 0; kb < 8; kb++) mbar_expect(bar + (B_OA + kb) * 8, 16384);
      }
    }
    uint32_t gate[32], xv[32];
    const size_t off = (size_t)(orow + warp * 16 + g) * (D_ / 2) + ocol / 2 + t;
#pragma unroll
    for (int j = 0; j < 16; j++) {
      xv[2 * j] = ((const uint32_t*)P.x)[off + j * 4];
      xv[2 * j + 1] = ((const uint32_t*)P.x)[off + 8 * 256 + j * 4];
    }
#pragma unroll
    for (int i = 0; i < 32; i++) {
      const float ha = 0.5f * acc[2 * i], hb = 0.5f * acc[2 * i + 1];
      gate[i] = packbf(fmaf(ha, tanh_fast(ha), ha), fmaf(hb, tanh_fast(hb), hb));
    }
#pragma unroll
    for (int i = 0; i < 64; i++) acc[i] = 0.f;
    fence_regs<64>(acc);
    fence_regs<32>(xv);
#pragma unroll 1
    for (int kb = 0; kb < 6; kb++) mbar_wait(bar + (B_OA + kb) * 8, 1);
    if (warp == 3) {
      mbar_wait(bar + B_T1 * 8, 0);
      if (elect1()) cnt_add_rel(C_O + quarter);
    }
    mbar_wait(bar + B_ATT * 8, 0);
    if (elect1()) tma2d(sm + wo_b(6) + warp * 8192, &P.tmWo, ocol + (warp & 1) * 64, (6 + (warp >> 1)) * 64, bar + (B_OA + 6 + (warp >> 1)) * 8);
    nbar(5, 128);
    mbar_wait(bar + (B_OA + 6) * 8, 1);
    mbar_wait(bar + (B_OA + 7) * 8, 1);
#pragma unroll 2
    for (int kb = 0; kb < 8; kb++) {
      mbar_wait(bar + (B_KV + kb) * 8, 1);
      const uint64_t da = opaque(cdesc(0, 16, 1024, 1) + kb * 512), db = opaque(cdesc(0, 8192, 1024, 1) + (wo_b(kb) >> 4));
      wfence();
#pragma unroll
      for (int k = 0; k < 4; k++) mm128t(acc, da + k * 2, db + k * 128, 1);
      wcommit();
    }
    wwait<0>();
    fence_regs<64>(acc);
    {
      const int r = warp * 16 + ((lane >> 3) & 1) * 8 + (lane & 7);
      const uint32_t stg = sm + 98304 + r * 128;
#pragma unroll
      for (int j = 0; j < 8; j++) {
        uint32_t v[4];
#pragma unroll
        for (int i = 0; i < 4; i++)
          v[i] = packbf(fmaf(acc[8 * j + 2 * i], bflo(gate[4 * j + i]), bflo(xv[4 * j + i])), fmaf(acc[8 * j + 2 * i + 1], bfhi(gate[4 * j + i]), bfhi(xv[4 * j + i])));
        stsm4(stg + (j >> 2) * 8192 + ((((j & 3) * 2 + (lane >> 4)) ^ (lane & 7)) << 4), v[0], v[1], v[2], v[3]);
        if ((j & 3) == 3) {
          fence_async_smem();
          __syncwarp();
          if (elect1()) { tma2d_st(&P.tmOut, sm + 98304 + (j >> 2) * 8192 + warp * 2048, ocol + (j >> 2) * 64, orow + warp * 16); bulk_commit(); }
        }
      }
      if (elect1()) asm volatile("cp.async.bulk.wait_group.read 0;" ::: "memory");
    }
  } else {
    asm volatile("setmaxnreg.dec.sync.aligned.u32 120;");
    float f0[12], f1[12]; uint32_t h0[10], h1[10];
#pragma unroll
    for (int i = 0; i < 12; i++) { f0[i] = 0.f; f1[i] = 0.f; }
#pragma unroll
    for (int i = 0; i < 10; i++) { h0[i] = 0; h1[i] = 0; }
    fence_regs<12>(f0); fence_regs<12>(f1); fence_regs<10>(h0); fence_regs<10>(h1);
    mbar_wait(bar + B_PUB * 8, 0);
    const uint64_t segs = P.segs[wg];
    const int nseg = wg == 1 ? 4 : 3;
    const uint32_t* qbase = (const uint32_t*)(g_qkv + (head * S_ + quarter * 512 + warp * 16 + g) * 2);
    const int sw = ((g >> 2) & 1) * 4;
    uint32_t qn[4];
    {
      const uint32_t* qp = qbase + ((segs >> 12) & 15) * 512;
      qn[0] = __ldcg(qp + (t ^ sw)); qn[1] = __ldcg(qp + 64 + (t ^ sw)); qn[2] = __ldcg(qp + ((t + 4) ^ sw)); qn[3] = __ldcg(qp + 64 + ((t + 4) ^ sw));
    }
    mbar_wait(bar + B_OK * 8, 0);
    const uint32_t okm = __shfl_sync(~0u, *(volatile uint32_t*)(smp + SM_OK), 0);
#pragma unroll 1
    for (int sg = 0; sg < nseg; sg++) {
      const uint32_t sd = (uint32_t)(segs >> (16 * sg));
      const int tile = (sd >> 12) & 15, t0 = (sd >> 8) & 15, t1 = (sd >> 4) & 15, mode = sd & 15;
      const int rg0 = quarter * 32 + tile * 4;
      uint32_t q[4] = {qn[0], qn[1], qn[2], qn[3]};
      fence_regs<4>(q);
      {
        const uint32_t* qp = qbase + (sd >> 28) * 512;
        qn[0] = __ldcg(qp + (t ^ sw)); qn[1] = __ldcg(qp + 64 + (t ^ sw)); qn[2] = __ldcg(qp + ((t + 4) ^ sw)); qn[3] = __ldcg(qp + 64 + ((t + 4) ^ sw));
      }
      const bool fast = ((okm >> (tile * 4)) & 15u) == 15u;
      bool tc = true;
      if (!fast) {
        if (mode & 1) continue;
        for (int i = 0; i < 8; i++) mbar_wait(bar + (B_KV + i) * 8, 0);
        tc = ((__shfl_sync(~0u, *(volatile uint32_t*)(smp + SM_OK2), 0) >> (tile * 4)) & 15u) == 15u;
      }
      if (!tc) {
        att_fallback(head, rg0 * 16, tid & 127, smp, smp + 65536);
      } else {
        float o[12];
#pragma unroll
        for (int i = 0; i < 12; i++) o[i] = 0.f;
        fence_regs<12>(o);
        if (fast) att_segment(o, q, t0, t1, sm, f0, f1, h0, h1);
        else att_exact(o, q, sm);
        float4* pp = g_part + ((bid * 2 + (tile != 0)) * 3) * 128 + (tid & 127);
        if (mode == 3) {
          const uint4* hp = g_hp + (head * 4 + quarter) * 5 * 128 + (tid & 127);
          uint4 u[5];
#pragma unroll 1
          for (int it = 0; it < (1 << 16); it++) {
            bool ok = true;
#pragma unroll
            for (int i = 0; i < 5; i++) u[i] = ldv4(hp + i * 128);
#pragma unroll
            for (int i = 0; i < 5; i++) ok = ok && u[i].y == tag && u[i].w == tag;
            if (__all_sync(~0u, ok)) break;
            __nanosleep(100);
          }
#pragma unroll
          for (int i = 0; i < 4; i++) { o[2 * i] += __uint_as_float(u[i].x); o[2 * i + 1] += __uint_as_float(u[i].z); }
          o[8] += __uint_as_float(u[4].x); o[10] += __uint_as_float(u[4].z);
        }
        if (mode & 1) {
          pp[0] = make_float4(o[0], o[1], o[2], o[3]); pp[128] = make_float4(o[4], o[5], o[6], o[7]); pp[256] = make_float4(o[8], o[10], 0.f, 0.f);
          nbar_arrive(6 + (tile != 0), 256);
          continue;
        }
        if (mode == 2 && fast) {
          nbar(6 + (tile != 0), 256);
          const float4 a = pp[0], b = pp[128], c = pp[256];
          o[0] += a.x; o[1] += a.y; o[2] += a.z; o[3] += a.w; o[4] += b.x; o[5] += b.y; o[6] += b.z; o[7] += b.w; o[8] += c.x; o[10] += c.y;
        }
        const float r0 = __fdividef(1.f, o[8]), r1 = __fdividef(1.f, o[10]);
        uint32_t* Op = (uint32_t*)(g_o + (size_t)((rg0 + warp) * 16) * D_ + head * 16);
        const uint32_t a0 = packbf(o[0] * r0, o[1] * r0), a1 = packbf(o[4] * r0, o[5] * r0), b0 = packbf(o[2] * r1, o[3] * r1), b1 = packbf(o[6] * r1, o[7] * r1);
        const bool hi = t & 2;
        const uint32_t xa = __shfl_xor_sync(~0u, hi ? a0 : a1, 2), xb = __shfl_xor_sync(~0u, hi ? b0 : b1, 2);
        uint2* O2 = (uint2*)Op + (t & 1) * 2 + (t >> 1);
        O2[g * 128] = hi ? make_uint2(xa, a1) : make_uint2(a0, xa);
        O2[(g + 8) * 128] = hi ? make_uint2(xb, b1) : make_uint2(b0, xb);
      }
      nbar(2 + wg, 128);
      if (tile < 6 && lane == 0) mbar_arrive(bar + B_T1 * 8);
    }
    __syncwarp();
    if (lane == 0) mbar_arrive(bar + B_ATT * 8);
    if (wg == 2) {
      if (warp == 0) {
        mbar_wait(bar + B_ATT * 8, 0);
        if (elect1()) { cnt_add_rel(C_OL + quarter * 8 + (head >> 2)); }
      }
    } else if (elect1()) {
      const int kb = wg * 4 + warp, orow = rb * 128 + (nt >> 2) * 64;
      const bool late = ((orow >> 6) & 7) >= 6;
      if (late) mbar_wait(bar + B_ATT * 8, 0);
      cnt_wait(late ? C_OL + (orow >> 9) * 8 + kb : C_O + (orow >> 9), tag * (late ? 4 : 32));
      mbar_wait(bar + B_ATT * 8, 0);
      tma2d(sm + kb * 8192, &P.tmO, kb * 64, orow, bar + (B_KV + kb) * 8);
      mbar_expect(bar + (B_KV + kb) * 8, 8192);
    }
  }
}

typedef CUresult (*EncFn)(CUtensorMap*, CUtensorMapDataType, cuuint32_t, void*, const cuuint64_t*, const cuuint64_t*, const cuuint32_t*,
                          const cuuint32_t*, CUtensorMapInterleave, CUtensorMapSwizzle, CUtensorMapL2promotion, CUtensorMapFloatOOBfill);
static EncFn g_enc = nullptr;
static void mk2d(CUtensorMap* m, const void* p, uint64_t cols, uint64_t rows, uint32_t bc, uint32_t br, CUtensorMapSwizzle sw) {
  cuuint64_t dims[2] = {cols, rows}, str[1] = {cols * 2};
  cuuint32_t box[2] = {bc, br}, es[2] = {1, 1};
  g_enc(m, CU_TENSOR_MAP_DATA_TYPE_BFLOAT16, 2, (void*)p, dims, str, box, es, CU_TENSOR_MAP_INTERLEAVE_NONE, sw,
        CU_TENSOR_MAP_L2_PROMOTION_L2_256B, CU_TENSOR_MAP_FLOAT_OOB_FILL_NONE);
}
extern "C" void kernel_launch(void* const* d_in, const int* in_sizes, int n_in, void* d_out, int out_size) {
  const bf16* x = (const bf16*)d_in[0];
  const bf16* wqkv = (const bf16*)d_in[1];
  const bf16* wo = (const bf16*)d_in[2];
  const bf16* w_in = (const bf16*)d_in[4];
  const bf16* w_sp = (const bf16*)d_in[5];
  const bf16* b_sp = (const bf16*)d_in[6];
  const bf16* w_out = (const bf16*)d_in[7];
  static void *p_u = nullptr, *p_o = nullptr;
  if (!g_enc) {
    cudaDriverEntryPointQueryResult qr;
    void* fn = nullptr;
    cudaGetDriverEntryPoint("cuTensorMapEncodeTiled", &fn, cudaEnableDefault, &qr);
    g_enc = (EncFn)fn;
    cudaGetSymbolAddress(&p_u, g_u); cudaGetSymbolAddress(&p_o, g_o);
    cudaFuncSetAttribute(k_mega, cudaFuncAttributeMaxDynamicSharedMemorySize, SM_TOTAL);
  }
  Params P;
  mk2d(&P.tmX, x, 512, 2048, 64, 64, CU_TENSOR_MAP_SWIZZLE_128B);
  mk2d(&P.tmWq, wqkv, 1536, 512, 64, 64, CU_TENSOR_MAP_SWIZZLE_128B);
  mk2d(&P.tmWi, w_in, 1792, 512, 64, 128, CU_TENSOR_MAP_SWIZZLE_128B);
  mk2d(&P.tmWsp, w_sp, 2048, 2048, 64, 64, CU_TENSOR_MAP_SWIZZLE_128B);
  mk2d(&P.tmUst, p_u, 896, 2048, 112, 128, CU_TENSOR_MAP_SWIZZLE_NONE);
  mk2d(&P.tmU, p_u, 896, 2048, 64, 64, CU_TENSOR_MAP_SWIZZLE_128B);
  mk2d(&P.tmWout, w_out, 512, 896, 64, 64, CU_TENSOR_MAP_SWIZZLE_128B);
  mk2d(&P.tmO, p_o, 512, 2048, 64, 64, CU_TENSOR_MAP_SWIZZLE_128B);
  mk2d(&P.tmWo, wo, 512, 512, 64, 64, CU_TENSOR_MAP_SWIZZLE_128B);
  mk2d(&P.tmSq, wqkv, 1536, 512, 32, 256, CU_TENSOR_MAP_SWIZZLE_NONE);
  mk2d(&P.tmSi, w_in, 1792, 512, 32, 256, CU_TENSOR_MAP_SWIZZLE_NONE);
  mk2d(&P.tmOut, d_out, 512, 2048, 64, 16, CU_TENSOR_MAP_SWIZZLE_128B);
  P.x = x; P.bsp = b_sp; P.wsp = w_sp; P.wqkv = wqkv; P.win = w_in; P.wout = w_out; P.wo = wo; P.out = (bf16*)d_out;
  cudaLaunchConfig_t cfg = {};
  cfg.gridDim = dim3(132); cfg.blockDim = dim3(512); cfg.dynamicSmemBytes = SM_TOTAL; cfg.stream = cudaStreamPerThread;
  cudaLaunchAttribute at[1];
  at[0].id = cudaLaunchAttributeClusterDimension; at[0].val.clusterDim.x = 2; at[0].val.clusterDim.y = 1; at[0].val.clusterDim.z = 1;
  cfg.attrs = at; cfg.numAttrs = 1;
  static int nclus = -1;
  if (nclus < 0) { if (cudaOccupancyMaxActiveClusters(&nclus, k_mega, &cfg) != cudaSuccess) nclus = 0; }
  const bool help = nclus >= 66;
  if (!help) cfg.gridDim = dim3(128);
  const uint64_t sb = help ? SPLB + 1 : SPLB;
  P.segs[0] = 0x0000608030800002ull + (SPLA << 4);
  P.segs[1] = (help ? 0x7203508020800081ull : 0x7001508020800081ull) + (SPLA << 8) + (sb << 52);
  P.segs[2] = 0x0000708240801080ull + (sb << 40);
  cudaLaunchKernelEx(&cfg, k_mega, P);
}
```
